```python
import torch

def _softmax(x, axis=-1):
    return torch.softmax(x, dim=axis)

def _gelu(x):
    return torch.nn.functional.gelu(x, approximate='tanh')

def _silu(x):
    return torch.nn.functional.silu(x)

def _sigmoid(x):
    return torch.sigmoid(x)

def _layernorm(x, axis=-1, eps=1e-05):
    m = x.mean(dim=axis, keepdim=True)
    v = x.var(dim=axis, keepdim=True, unbiased=False)
    return (x - m) / torch.sqrt(v + eps)

def _scatter_add(tgt, idx, src, axis=0):
    return tgt.clone().index_add_(axis, idx, src)

def _segment_sum(src, seg, n):
    out = torch.zeros((n,) + src.shape[1:], dtype=src.dtype)
    return out.index_add_(0, seg, src)

def _pad(x, pw):
    flat = tuple((v for pair in reversed(pw) for v in pair))
    return torch.nn.functional.pad(x, flat)
kernel_name = 'adaLN_cond__grouped_kv_mqa__dense_activation_relu__prompt'

def setup_inputs():

    _w = lambda a: (lambda t: t.to(torch.bfloat16) if t.is_floating_point() else t)(torch.as_tensor(a))

    def _A_setup():
        B, S, D, H = (1, 2048, 1024, 32)
        Dh = D // H
        return {'x': _w((lambda *s: torch.randn(*s, dtype=torch.bfloat16) * 0.05)(B, S, D)), 'wq': _w((lambda *s: torch.randn(*s, dtype=torch.bfloat16) * 0.05)(D, H * Dh)), 'wk': _w((lambda *s: torch.randn(*s, dtype=torch.bfloat16) * 0.05)(D, Dh)), 'wv': _w((lambda *s: torch.randn(*s, dtype=torch.bfloat16) * 0.05)(D, Dh)), 'wo': _w((lambda *s: torch.randn(*s, dtype=torch.bfloat16) * 0.05)(H * Dh, D))}
    _A_in = _A_setup()

    def _B_setup():
        B, S, D, Dff = (1, 2048, 1024, 3584)
        return {'x': _w((lambda *s: torch.randn(*s, dtype=torch.bfloat16) * 0.05)(B, S, D)), 'w1': _w((lambda *s: torch.randn(*s, dtype=torch.bfloat16) * 0.05)(D, Dff)), 'w2': _w((lambda *s: torch.randn(*s, dtype=torch.bfloat16) * 0.05)(Dff, D))}
    _B_in = _B_setup()
    return {'A_x': _A_in['x'], 'A_wq': _A_in['wq'], 'A_wk': _A_in['wk'], 'A_wv': _A_in['wv'], 'A_wo': _A_in['wo'], 'B_x': _B_in['x'], 'B_w1': _B_in['w1'], 'B_w2': _B_in['w2'], 'c': _w((lambda *s: torch.randn(*s, dtype=torch.bfloat16) * 0.2)(1, 1024) * 8.0), 'w_mod': _w((lambda *s: torch.randn(*s, dtype=torch.bfloat16) * 0.2)(1024, 6 * 1024) * 1024 ** (-0.5) * 8.0)}

def reference(A_x, A_wq, A_wk, A_wv, A_wo, B_x, B_w1, B_w2, c, w_mod):

    def _A_ref(x, wq, wk, wv, wo):
        B, S, D = x.shape
        H = 32
        Dh = D // H
        q = (lambda x, *d: x.permute(*d))((x @ wq).reshape(B, S, H, Dh), 0, 2, 1, 3)
        k = x @ wk
        v = x @ wv
        scores = torch.einsum('bhqd,bkd->bhqk', q, k) * Dh ** (-0.5)
        p = _softmax(scores, axis=-1)
        o = torch.einsum('bhqk,bkd->bhqd', p, v)
        return (lambda x, *d: x.permute(*d))(o, 0, 2, 1, 3).reshape(B, S, H * Dh) @ wo

    def _B_ref(x, w1, w2):
        h = torch.einsum('bsd,df->bsf', x, w1)
        zero = torch.zeros_like(h)
        h = torch.maximum(h, zero)
        return torch.einsum('bsf,fd->bsd', h, w2)
    x = A_x
    mod = (_silu(c) @ w_mod).reshape(c.shape[0], 6, 1, -1)
    sa, ca, ga, sb, cb, gb = (mod[:, 0].clone(), mod[:, 1].clone(), mod[:, 2].clone(), mod[:, 3].clone(), mod[:, 4].clone(), mod[:, 5].clone())
    h = _layernorm(x, axis=-1) * (1 + ca) + sa
    x = x + ga * _A_ref(h, A_wq, A_wk, A_wv, A_wo)
    h = _layernorm(x, axis=-1) * (1 + cb) + sb
    x = x + gb * _B_ref(h, B_w1, B_w2)
    return x
```

```cpp
#include <cuda_runtime.h>
#include <cuda_bf16.h>
#include <cuda.h>
#include <stdint.h>

typedef __nv_bfloat16 bf16;

constexpr int S_ = 2048, D_ = 1024, DFF = 3584, NQKV = 1088;

__device__ __align__(1024) bf16 g_h[S_ * D_];
__device__ __align__(1024) bf16 g_wqkvT[NQKV * D_];
__device__ __align__(1024) bf16 g_q[S_ * D_];
__device__ __align__(1024) bf16 g_k[S_ * 32];
__device__ __align__(1024) bf16 g_vT[32 * S_];
__device__ __align__(1024) bf16 g_o[S_ * D_];
__device__ __align__(1024) bf16 g_x1[S_ * D_];
__device__ __align__(1024) bf16 g_hff[S_ * DFF];
__device__ __align__(1024) float g_mod[6 * D_];

__device__ __forceinline__ uint32_t smem_u32(const void* p) { return (uint32_t)__cvta_generic_to_shared(p); }

__device__ __forceinline__ void mbar_init(uint32_t bar, uint32_t count) {
  asm volatile("mbarrier.init.shared::cta.b64 [%0], %1;" ::"r"(bar), "r"(count) : "memory");
}
__device__ __forceinline__ void mbar_expect_tx(uint32_t bar, uint32_t bytes) {
  asm volatile("mbarrier.arrive.expect_tx.shared::cta.b64 _, [%0], %1;" ::"r"(bar), "r"(bytes) : "memory");
}
__device__ __forceinline__ void mbar_arrive(uint32_t bar) {
  asm volatile("mbarrier.arrive.shared::cta.b64 _, [%0];" ::"r"(bar) : "memory");
}
__device__ __forceinline__ bool mbar_try_wait(uint32_t bar, uint32_t parity) {
  uint32_t ok;
  asm volatile(
      "{\n.reg .pred p;\n"
      "mbarrier.try_wait.parity.shared::cta.b64 p, [%1], %2;\n"
      "selp.u32 %0, 1, 0, p;\n}\n"
      : "=r"(ok)
      : "r"(bar), "r"(parity)
      : "memory");
  return ok != 0;
}
__device__ __forceinline__ void mbar_wait(uint32_t bar, uint32_t parity) {
  if (mbar_try_wait(bar, parity)) return;
  uint32_t it = 0;
  while (!mbar_try_wait(bar, parity)) {
    if (++it > (1u << 24)) __trap();
  }
}
__device__ __forceinline__ void tma_load_2d(uint32_t dst, const CUtensorMap* map, uint32_t bar, int c0, int c1) {
  asm volatile(
      "cp.async.bulk.tensor.2d.shared::cluster.global.mbarrier::complete_tx::bytes [%0], [%1, {%3, %4}], [%2];"
      ::"r"(dst), "l"(map), "r"(bar), "r"(c0), "r"(c1)
      : "memory");
}
__device__ __forceinline__ void tma_load_3d(uint32_t dst, const CUtensorMap* map, uint32_t bar, int c0, int c1, int c2) {
  asm volatile(
      "cp.async.bulk.tensor.3d.shared::cluster.global.mbarrier::complete_tx::bytes [%0], [%1, {%3, %4, %5}], [%2];"
      ::"r"(dst), "l"(map), "r"(bar), "r"(c0), "r"(c1), "r"(c2)
      : "memory");
}
__device__ __forceinline__ void tma_load_2d_mc(uint32_t dst, const CUtensorMap* map, uint32_t bar, int c0, int c1, uint16_t mask) {
  asm volatile(
      "cp.async.bulk.tensor.2d.shared::cluster.global.mbarrier::complete_tx::bytes.multicast::cluster [%0], [%1, {%3, %4}], [%2], %5;"
      ::"r"(dst), "l"(map), "r"(bar), "r"(c0), "r"(c1), "h"(mask)
      : "memory");
}
__device__ __forceinline__ void tma_load_3d_mc(uint32_t dst, const CUtensorMap* map, uint32_t bar, int c0, int c1, int c2, uint16_t mask) {
  asm volatile(
      "cp.async.bulk.tensor.3d.shared::cluster.global.mbarrier::complete_tx::bytes.multicast::cluster [%0], [%1, {%3, %4, %5}], [%2], %6;"
      ::"r"(dst), "l"(map), "r"(bar), "r"(c0), "r"(c1), "r"(c2), "h"(mask)
      : "memory");
}
__device__ __forceinline__ uint32_t mapa_u32(uint32_t addr, uint32_t rank) {
  uint32_t r;
  asm("mapa.shared::cluster.u32 %0, %1, %2;" : "=r"(r) : "r"(addr), "r"(rank));
  return r;
}
__device__ __forceinline__ void mbar_arrive_cluster(uint32_t cluster_addr) {
  asm volatile("mbarrier.arrive.shared::cluster.b64 _, [%0];" ::"r"(cluster_addr) : "memory");
}
__device__ __forceinline__ void cluster_arrive() { asm volatile("barrier.cluster.arrive.release.aligned;" ::: "memory"); }
__device__ __forceinline__ void cluster_wait() { asm volatile("barrier.cluster.wait.acquire.aligned;" ::: "memory"); }
__device__ __forceinline__ uint32_t cluster_ctarank() {
  uint32_t r;
  asm("mov.u32 %0, %%cluster_ctarank;" : "=r"(r));
  return r;
}
__device__ __forceinline__ void tma_store_2d(const CUtensorMap* map, uint32_t src, int c0, int c1) {
  asm volatile("cp.async.bulk.tensor.2d.global.shared::cta.bulk_group [%0, {%2, %3}], [%1];"
               ::"l"(map), "r"(src), "r"(c0), "r"(c1)
               : "memory");
}
__device__ __forceinline__ void bulk_commit() { asm volatile("cp.async.bulk.commit_group;" ::: "memory"); }
__device__ __forceinline__ void bulk_wait_read0() { asm volatile("cp.async.bulk.wait_group.read 0;" ::: "memory"); }
__device__ __forceinline__ void bulk_wait0() { asm volatile("cp.async.bulk.wait_group 0;" ::: "memory"); }
__device__ __forceinline__ void fence_proxy_async() { asm volatile("fence.proxy.async.shared::cta;" ::: "memory"); }
__device__ __forceinline__ void fence_mbar_init() { asm volatile("fence.mbarrier_init.release.cluster;" ::: "memory"); }
__device__ __forceinline__ void prefetch_tmap(const CUtensorMap* map) {
  asm volatile("prefetch.tensormap [%0];" ::"l"(map) : "memory");
}
__device__ __forceinline__ void wgmma_fence() { asm volatile("wgmma.fence.sync.aligned;" ::: "memory"); }
__device__ __forceinline__ void wgmma_commit() { asm volatile("wgmma.commit_group.sync.aligned;" ::: "memory"); }
template <int N>
__device__ __forceinline__ void wgmma_wait() { asm volatile("wgmma.wait_group.sync.aligned %0;" ::"n"(N) : "memory"); }
__device__ __forceinline__ void named_bar_sync(int id, int nthreads) {
  asm volatile("bar.sync %0, %1;" ::"r"(id), "r"(nthreads) : "memory");
}
__device__ __forceinline__ void pdl_wait() { asm volatile("griddepcontrol.wait;" ::: "memory"); }
__device__ __forceinline__ void pdl_launch() { asm volatile("griddepcontrol.launch_dependents;" ::: "memory"); }

__device__ __forceinline__ uint32_t pack_bf16(float lo, float hi) {
  uint32_t r;
  asm("cvt.rn.bf16x2.f32 %0, %1, %2;" : "=r"(r) : "f"(hi), "f"(lo));
  return r;
}
__device__ __forceinline__ uint32_t pack_bf16_relu(float lo, float hi) {
  uint32_t r;
  asm("cvt.rn.relu.bf16x2.f32 %0, %1, %2;" : "=r"(r) : "f"(hi), "f"(lo));
  return r;
}
__device__ __forceinline__ float bf16_lo(uint32_t v) { return __uint_as_float(v << 16); }
__device__ __forceinline__ float bf16_hi(uint32_t v) { return __uint_as_float(v & 0xffff0000u); }
__device__ __forceinline__ float bf16r(float x) { return __bfloat162float(__float2bfloat16_rn(x)); }
__device__ __forceinline__ void stmatrix_x4(uint32_t addr, uint32_t r0, uint32_t r1, uint32_t r2, uint32_t r3) {
  asm volatile("stmatrix.sync.aligned.m8n8.x4.shared.b16 [%0], {%1, %2, %3, %4};"
               ::"r"(addr), "r"(r0), "r"(r1), "r"(r2), "r"(r3)
               : "memory");
}
__device__ __forceinline__ void ldmatrix_x4(uint32_t addr, uint32_t& r0, uint32_t& r1, uint32_t& r2, uint32_t& r3) {
  asm volatile("ldmatrix.sync.aligned.m8n8.x4.shared.b16 {%0, %1, %2, %3}, [%4];"
               : "=r"(r0), "=r"(r1), "=r"(r2), "=r"(r3)
               : "r"(addr)
               : "memory");
}
__device__ __forceinline__ uint64_t make_desc(uint32_t addr, uint32_t lbo_bytes, uint32_t sbo_bytes, uint32_t layout) {
  return (uint64_t)((addr & 0x3FFFF) >> 4) | ((uint64_t)(lbo_bytes >> 4) << 16) | ((uint64_t)(sbo_bytes >> 4) << 32) |
         ((uint64_t)layout << 62);
}

__device__ __forceinline__ void wgmma_ss_n136_tb0(float (&d)[68], uint64_t da, uint64_t db, int scale_d) {
  asm volatile("{\n.reg .pred p;\nsetp.ne.b32 p, %70, 0;\n"
    "wgmma.mma_async.sync.aligned.m64n136k16.f32.bf16.bf16 {%0, %1, %2, %3, %4, %5, %6, %7, %8, %9, %10, %11, %12, %13, %14, %15, %16, %17, %18, %19, %20, %21, %22, %23, %24, %25, %26, %27, %28, %29, %30, %31, %32, %33, %34, %35, %36, %37, %38, %39, %40, %41, %42, %43, %44, %45, %46, %47, %48, %49, %50, %51, %52, %53, %54, %55, %56, %57, %58, %59, %60, %61, %62, %63, %64, %65, %66, %67}, %68, %69, p, 1, 1, 0, 0;\n}\n"
    : "+f"(d[0]), "+f"(d[1]), "+f"(d[2]), "+f"(d[3]), "+f"(d[4]), "+f"(d[5]), "+f"(d[6]), "+f"(d[7]), "+f"(d[8]), "+f"(d[9]), "+f"(d[10]), "+f"(d[11]), "+f"(d[12]), "+f"(d[13]), "+f"(d[14]), "+f"(d[15]), "+f"(d[16]), "+f"(d[17]), "+f"(d[18]), "+f"(d[19]), "+f"(d[20]), "+f"(d[21]), "+f"(d[22]), "+f"(d[23]), "+f"(d[24]), "+f"(d[25]), "+f"(d[26]), "+f"(d[27]), "+f"(d[28]), "+f"(d[29]), "+f"(d[30]), "+f"(d[31]), "+f"(d[32]), "+f"(d[33]), "+f"(d[34]), "+f"(d[35]), "+f"(d[36]), "+f"(d[37]), "+f"(d[38]), "+f"(d[39]), "+f"(d[40]), "+f"(d[41]), "+f"(d[42]), "+f"(d[43]), "+f"(d[44]), "+f"(d[45]), "+f"(d[46]), "+f"(d[47]), "+f"(d[48]), "+f"(d[49]), "+f"(d[50]), "+f"(d[51]), "+f"(d[52]), "+f"(d[53]), "+f"(d[54]), "+f"(d[55]), "+f"(d[56]), "+f"(d[57]), "+f"(d[58]), "+f"(d[59]), "+f"(d[60]), "+f"(d[61]), "+f"(d[62]), "+f"(d[63]), "+f"(d[64]), "+f"(d[65]), "+f"(d[66]), "+f"(d[67])
    : "l"(da), "l"(db), "r"(scale_d));
}
__device__ __forceinline__ void wgmma_ss_n128_tb1(float (&d)[64], uint64_t da, uint64_t db, int scale_d) {
  asm volatile("{\n.reg .pred p;\nsetp.ne.b32 p, %66, 0;\n"
    "wgmma.mma_async.sync.aligned.m64n128k16.f32.bf16.bf16 {%0, %1, %2, %3, %4, %5, %6, %7, %8, %9, %10, %11, %12, %13, %14, %15, %16, %17, %18, %19, %20, %21, %22, %23, %24, %25, %26, %27, %28, %29, %30, %31, %32, %33, %34, %35, %36, %37, %38, %39, %40, %41, %42, %43, %44, %45, %46, %47, %48, %49, %50, %51, %52, %53, %54, %55, %56, %57, %58, %59, %60, %61, %62, %63}, %64, %65, p, 1, 1, 0, 1;\n}\n"
    : "+f"(d[0]), "+f"(d[1]), "+f"(d[2]), "+f"(d[3]), "+f"(d[4]), "+f"(d[5]), "+f"(d[6]), "+f"(d[7]), "+f"(d[8]), "+f"(d[9]), "+f"(d[10]), "+f"(d[11]), "+f"(d[12]), "+f"(d[13]), "+f"(d[14]), "+f"(d[15]), "+f"(d[16]), "+f"(d[17]), "+f"(d[18]), "+f"(d[19]), "+f"(d[20]), "+f"(d[21]), "+f"(d[22]), "+f"(d[23]), "+f"(d[24]), "+f"(d[25]), "+f"(d[26]), "+f"(d[27]), "+f"(d[28]), "+f"(d[29]), "+f"(d[30]), "+f"(d[31]), "+f"(d[32]), "+f"(d[33]), "+f"(d[34]), "+f"(d[35]), "+f"(d[36]), "+f"(d[37]), "+f"(d[38]), "+f"(d[39]), "+f"(d[40]), "+f"(d[41]), "+f"(d[42]), "+f"(d[43]), "+f"(d[44]), "+f"(d[45]), "+f"(d[46]), "+f"(d[47]), "+f"(d[48]), "+f"(d[49]), "+f"(d[50]), "+f"(d[51]), "+f"(d[52]), "+f"(d[53]), "+f"(d[54]), "+f"(d[55]), "+f"(d[56]), "+f"(d[57]), "+f"(d[58]), "+f"(d[59]), "+f"(d[60]), "+f"(d[61]), "+f"(d[62]), "+f"(d[63])
    : "l"(da), "l"(db), "r"(scale_d));
}
__device__ __forceinline__ void wgmma_ss_n224_tb1(float (&d)[112], uint64_t da, uint64_t db, int scale_d) {
  asm volatile("{\n.reg .pred p;\nsetp.ne.b32 p, %114, 0;\n"
    "wgmma.mma_async.sync.aligned.m64n224k16.f32.bf16.bf16 {%0, %1, %2, %3, %4, %5, %6, %7, %8, %9, %10, %11, %12, %13, %14, %15, %16, %17, %18, %19, %20, %21, %22, %23, %24, %25, %26, %27, %28, %29, %30, %31, %32, %33, %34, %35, %36, %37, %38, %39, %40, %41, %42, %43, %44, %45, %46, %47, %48, %49, %50, %51, %52, %53, %54, %55, %56, %57, %58, %59, %60, %61, %62, %63, %64, %65, %66, %67, %68, %69, %70, %71, %72, %73, %74, %75, %76, %77, %78, %79, %80, %81, %82, %83, %84, %85, %86, %87, %88, %89, %90, %91, %92, %93, %94, %95, %96, %97, %98, %99, %100, %101, %102, %103, %104, %105, %106, %107, %108, %109, %110, %111}, %112, %113, p, 1, 1, 0, 1;\n}\n"
    : "+f"(d[0]), "+f"(d[1]), "+f"(d[2]), "+f"(d[3]), "+f"(d[4]), "+f"(d[5]), "+f"(d[6]), "+f"(d[7]), "+f"(d[8]), "+f"(d[9]), "+f"(d[10]), "+f"(d[11]), "+f"(d[12]), "+f"(d[13]), "+f"(d[14]), "+f"(d[15]), "+f"(d[16]), "+f"(d[17]), "+f"(d[18]), "+f"(d[19]), "+f"(d[20]), "+f"(d[21]), "+f"(d[22]), "+f"(d[23]), "+f"(d[24]), "+f"(d[25]), "+f"(d[26]), "+f"(d[27]), "+f"(d[28]), "+f"(d[29]), "+f"(d[30]), "+f"(d[31]), "+f"(d[32]), "+f"(d[33]), "+f"(d[34]), "+f"(d[35]), "+f"(d[36]), "+f"(d[37]), "+f"(d[38]), "+f"(d[39]), "+f"(d[40]), "+f"(d[41]), "+f"(d[42]), "+f"(d[43]), "+f"(d[44]), "+f"(d[45]), "+f"(d[46]), "+f"(d[47]), "+f"(d[48]), "+f"(d[49]), "+f"(d[50]), "+f"(d[51]), "+f"(d[52]), "+f"(d[53]), "+f"(d[54]), "+f"(d[55]), "+f"(d[56]), "+f"(d[57]), "+f"(d[58]), "+f"(d[59]), "+f"(d[60]), "+f"(d[61]), "+f"(d[62]), "+f"(d[63]), "+f"(d[64]), "+f"(d[65]), "+f"(d[66]), "+f"(d[67]), "+f"(d[68]), "+f"(d[69]), "+f"(d[70]), "+f"(d[71]), "+f"(d[72]), "+f"(d[73]), "+f"(d[74]), "+f"(d[75]), "+f"(d[76]), "+f"(d[77]), "+f"(d[78]), "+f"(d[79]), "+f"(d[80]), "+f"(d[81]), "+f"(d[82]), "+f"(d[83]), "+f"(d[84]), "+f"(d[85]), "+f"(d[86]), "+f"(d[87]), "+f"(d[88]), "+f"(d[89]), "+f"(d[90]), "+f"(d[91]), "+f"(d[92]), "+f"(d[93]), "+f"(d[94]), "+f"(d[95]), "+f"(d[96]), "+f"(d[97]), "+f"(d[98]), "+f"(d[99]), "+f"(d[100]), "+f"(d[101]), "+f"(d[102]), "+f"(d[103]), "+f"(d[104]), "+f"(d[105]), "+f"(d[106]), "+f"(d[107]), "+f"(d[108]), "+f"(d[109]), "+f"(d[110]), "+f"(d[111])
    : "l"(da), "l"(db), "r"(scale_d));
}
__device__ __forceinline__ void wgmma_rs_n128_tb0(float (&d)[64], uint32_t a0, uint32_t a1, uint32_t a2, uint32_t a3, uint64_t db, int scale_d) {
  asm volatile("{\n.reg .pred p;\nsetp.ne.b32 p, %69, 0;\n"
    "wgmma.mma_async.sync.aligned.m64n128k16.f32.bf16.bf16 {%0, %1, %2, %3, %4, %5, %6, %7, %8, %9, %10, %11, %12, %13, %14, %15, %16, %17, %18, %19, %20, %21, %22, %23, %24, %25, %26, %27, %28, %29, %30, %31, %32, %33, %34, %35, %36, %37, %38, %39, %40, %41, %42, %43, %44, %45, %46, %47, %48, %49, %50, %51, %52, %53, %54, %55, %56, %57, %58, %59, %60, %61, %62, %63}, {%64, %65, %66, %67}, %68, p, 1, 1, 0;\n}\n"
    : "+f"(d[0]), "+f"(d[1]), "+f"(d[2]), "+f"(d[3]), "+f"(d[4]), "+f"(d[5]), "+f"(d[6]), "+f"(d[7]), "+f"(d[8]), "+f"(d[9]), "+f"(d[10]), "+f"(d[11]), "+f"(d[12]), "+f"(d[13]), "+f"(d[14]), "+f"(d[15]), "+f"(d[16]), "+f"(d[17]), "+f"(d[18]), "+f"(d[19]), "+f"(d[20]), "+f"(d[21]), "+f"(d[22]), "+f"(d[23]), "+f"(d[24]), "+f"(d[25]), "+f"(d[26]), "+f"(d[27]), "+f"(d[28]), "+f"(d[29]), "+f"(d[30]), "+f"(d[31]), "+f"(d[32]), "+f"(d[33]), "+f"(d[34]), "+f"(d[35]), "+f"(d[36]), "+f"(d[37]), "+f"(d[38]), "+f"(d[39]), "+f"(d[40]), "+f"(d[41]), "+f"(d[42]), "+f"(d[43]), "+f"(d[44]), "+f"(d[45]), "+f"(d[46]), "+f"(d[47]), "+f"(d[48]), "+f"(d[49]), "+f"(d[50]), "+f"(d[51]), "+f"(d[52]), "+f"(d[53]), "+f"(d[54]), "+f"(d[55]), "+f"(d[56]), "+f"(d[57]), "+f"(d[58]), "+f"(d[59]), "+f"(d[60]), "+f"(d[61]), "+f"(d[62]), "+f"(d[63])
    : "r"(a0), "r"(a1), "r"(a2), "r"(a3), "l"(db), "r"(scale_d));
}
__device__ __forceinline__ void wgmma_rs_n64_tb0(float (&d)[32], uint32_t a0, uint32_t a1, uint32_t a2, uint32_t a3, uint64_t db, int scale_d) {
  asm volatile("{\n.reg .pred p;\nsetp.ne.b32 p, %37, 0;\n"
    "wgmma.mma_async.sync.aligned.m64n64k16.f32.bf16.bf16 {%0, %1, %2, %3, %4, %5, %6, %7, %8, %9, %10, %11, %12, %13, %14, %15, %16, %17, %18, %19, %20, %21, %22, %23, %24, %25, %26, %27, %28, %29, %30, %31}, {%32, %33, %34, %35}, %36, p, 1, 1, 0;\n}\n"
    : "+f"(d[0]), "+f"(d[1]), "+f"(d[2]), "+f"(d[3]), "+f"(d[4]), "+f"(d[5]), "+f"(d[6]), "+f"(d[7]), "+f"(d[8]), "+f"(d[9]), "+f"(d[10]), "+f"(d[11]), "+f"(d[12]), "+f"(d[13]), "+f"(d[14]), "+f"(d[15]), "+f"(d[16]), "+f"(d[17]), "+f"(d[18]), "+f"(d[19]), "+f"(d[20]), "+f"(d[21]), "+f"(d[22]), "+f"(d[23]), "+f"(d[24]), "+f"(d[25]), "+f"(d[26]), "+f"(d[27]), "+f"(d[28]), "+f"(d[29]), "+f"(d[30]), "+f"(d[31])
    : "r"(a0), "r"(a1), "r"(a2), "r"(a3), "l"(db), "r"(scale_d));
}
__device__ __forceinline__ void wgmma_rs_n40_tb0(float (&d)[20], uint32_t a0, uint32_t a1, uint32_t a2, uint32_t a3, uint64_t db, int scale_d) {
  asm volatile("{\n.reg .pred p;\nsetp.ne.b32 p, %25, 0;\n"
    "wgmma.mma_async.sync.aligned.m64n40k16.f32.bf16.bf16 {%0, %1, %2, %3, %4, %5, %6, %7, %8, %9, %10, %11, %12, %13, %14, %15, %16, %17, %18, %19}, {%20, %21, %22, %23}, %24, p, 1, 1, 0;\n}\n"
    : "+f"(d[0]), "+f"(d[1]), "+f"(d[2]), "+f"(d[3]), "+f"(d[4]), "+f"(d[5]), "+f"(d[6]), "+f"(d[7]), "+f"(d[8]), "+f"(d[9]), "+f"(d[10]), "+f"(d[11]), "+f"(d[12]), "+f"(d[13]), "+f"(d[14]), "+f"(d[15]), "+f"(d[16]), "+f"(d[17]), "+f"(d[18]), "+f"(d[19])
    : "r"(a0), "r"(a1), "r"(a2), "r"(a3), "l"(db), "r"(scale_d));
}

#define TL(k, w)

__device__ __align__(16) uint2 g_modx[2048];
#define PRE_SLEEP 100
__device__ unsigned int g_epoch;

__device__ __forceinline__ float silu_bf16(float v) { return bf16r(v / (1.0f + __expf(-v))); }
__device__ __forceinline__ void bf16r2(float& a, float& b) {
  const uint32_t u = pack_bf16(a, b);
  a = bf16_lo(u); b = bf16_hi(u);
}
__device__ __forceinline__ uint32_t bmul2(uint32_t a, uint32_t b) {
  uint32_t r;
  asm("mul.rn.bf16x2 %0, %1, %2;" : "=r"(r) : "r"(a), "r"(b));
  return r;
}
__device__ __forceinline__ uint32_t badd2(uint32_t a, uint32_t b) {
  uint32_t r;
  asm("add.rn.bf16x2 %0, %1, %2;" : "=r"(r) : "r"(a), "r"(b));
  return r;
}
__device__ __forceinline__ uint32_t bsub2(uint32_t a, uint32_t b) {
  uint32_t r;
  asm("sub.rn.bf16x2 %0, %1, %2;" : "=r"(r) : "r"(a), "r"(b));
  return r;
}
__device__ __forceinline__ void ldmatrix_x4_trans(uint32_t addr, uint32_t& r0, uint32_t& r1, uint32_t& r2, uint32_t& r3) {
  asm volatile("ldmatrix.sync.aligned.m8n8.x4.trans.shared.b16 {%0, %1, %2, %3}, [%4];"
               : "=r"(r0), "=r"(r1), "=r"(r2), "=r"(r3)
               : "r"(addr)
               : "memory");
}

__global__ void __launch_bounds__(512, 1) pre_kernel(const bf16* __restrict__ x, const bf16* __restrict__ c,
                                                     const bf16* __restrict__ wmod, const bf16* __restrict__ wq,
                                                     const bf16* __restrict__ wk, const bf16* __restrict__ wv) {
  __shared__ __align__(128) uint8_t s_tr[2 * 8192];
  __shared__ __align__(16) uint32_t s_mod[1024];
  __shared__ float s_c[1024];
  __shared__ float s_red[16][16];
  const int tid = threadIdx.x, warp = tid >> 5, lane = tid & 31;
  const bool main_blk = blockIdx.x < 128;
  pdl_launch();
  TL(0, 0);
  const int half = tid >> 8, ht = tid & 255;
  const int tt = blockIdx.x * 2 + half;
  const int kt = tt & 15, nt = tt >> 4;
  uint4 tv[2];
  uint4 v[4];
  const int row = blockIdx.x * 16 + warp;
  auto transpose = [&]() {
    const uint32_t sb = smem_u32(s_tr) + half * 8192;
#pragma unroll
    for (int p = 0; p < 2; p++) {
      const int r = p * 32 + (ht >> 3);
      const int f = (r & 1) | (((r >> 3) & 3) << 1);
      *reinterpret_cast<uint4*>(s_tr + half * 8192 + r * 128 + (((ht & 7) ^ f) << 4)) = tv[p];
    }
    __syncthreads();
    const int w8 = ht >> 5, mi = lane & 7, mj = lane >> 3;
    const int n = w8 * 8 + (lane >> 2);
    int drow;
    if (nt < 16) { const int col = nt * 64 + n; drow = (col >> 7) * 136 + (col & 127); }
    else drow = (n >> 3) * 136 + 128 + (n & 7);
#pragma unroll
    for (int kh = 0; kh < 2; kh++) {
      const int k = kh * 32 + (mi >> 1) * 8 + 2 * mj + (mi & 1);
      uint4 o;
      ldmatrix_x4_trans(sb + k * 128 + ((w8 ^ mi) << 4), o.x, o.y, o.z, o.w);
      *reinterpret_cast<uint4*>(g_wqkvT + (size_t)drow * 1024 + kt * 64 + kh * 32 + (lane & 3) * 8) = o;
    }
  };
  if (main_blk) {
    const int ct = tid & 1, rr = tid >> 1;
    uint4 w[4];
#pragma unroll
    for (int i = 0; i < 4; i++)
      w[i] = __ldcs(reinterpret_cast<const uint4*>(wmod + (size_t)(i * 256 + rr) * 6144 + blockIdx.x * 16 + ct * 8));
    const float c0 = __bfloat162float(c[tid]), c1 = __bfloat162float(c[tid + 512]);
    unsigned int tag;
    asm volatile("ld.volatile.global.u32 %0, [%1];" : "=r"(tag) : "l"(&g_epoch) : "memory");
    tag += 1u;
    s_c[tid] = silu_bf16(c0);
    s_c[tid + 512] = silu_bf16(c1);
    __syncthreads();
    float acc[8];
#pragma unroll
    for (int e = 0; e < 8; e++) acc[e] = 0.f;
#pragma unroll
    for (int i = 0; i < 4; i++) {
      const float cv = s_c[i * 256 + rr];
      acc[0] += cv * bf16_lo(w[i].x); acc[1] += cv * bf16_hi(w[i].x);
      acc[2] += cv * bf16_lo(w[i].y); acc[3] += cv * bf16_hi(w[i].y);
      acc[4] += cv * bf16_lo(w[i].z); acc[5] += cv * bf16_hi(w[i].z);
      acc[6] += cv * bf16_lo(w[i].w); acc[7] += cv * bf16_hi(w[i].w);
    }
#pragma unroll
    for (int e = 0; e < 4; e++) {
      const bool up = lane & 8;
      const float snd = up ? acc[e] : acc[e + 4], keep = up ? acc[e + 4] : acc[e];
      acc[e] = keep + __shfl_xor_sync(0xffffffffu, snd, 8);
    }
#pragma unroll
    for (int e = 0; e < 2; e++) {
      const bool up = lane & 4;
      const float snd = up ? acc[e] : acc[e + 2], keep = up ? acc[e + 2] : acc[e];
      acc[e] = keep + __shfl_xor_sync(0xffffffffu, snd, 4);
    }
    {
      const bool up = lane & 2;
      const float snd = up ? acc[0] : acc[1], keep = up ? acc[1] : acc[0];
      acc[0] = keep + __shfl_xor_sync(0xffffffffu, snd, 2);
    }
    acc[0] += __shfl_xor_sync(0xffffffffu, acc[0], 16);
    if (lane < 16) s_red[warp][(lane & 1) * 8 + (lane >> 1)] = acc[0];
    __syncthreads();
    if (tid < 16) {
      float s = 0.f;
#pragma unroll
      for (int i = 0; i < 16; i++) s += s_red[i][tid];
      s = bf16r(s);
      if (blockIdx.x >= 64) s = bf16r(1.0f + s);
      asm volatile("st.volatile.global.v2.u32 [%0], {%1, %2};" ::"l"(g_modx + blockIdx.x * 16 + tid), "r"(__float_as_uint(s)), "r"(tag) : "memory");
    }
#pragma unroll
    for (int i = 0; i < 4; i++) v[i] = *reinterpret_cast<const uint4*>(x + (size_t)row * D_ + i * 256 + lane * 8);
#pragma unroll
    for (int p = 0; p < 2; p++)
      tv[p] = __ldcs(reinterpret_cast<const uint4*>(wq + (size_t)(kt * 64 + p * 32 + (ht >> 3)) * 1024 + nt * 64 + (ht & 7) * 8));
    float s = 0.f;
#pragma unroll
    for (int i = 0; i < 4; i++)
      s += (bf16_lo(v[i].x) + bf16_hi(v[i].x)) + (bf16_lo(v[i].y) + bf16_hi(v[i].y)) + (bf16_lo(v[i].z) + bf16_hi(v[i].z)) +
           (bf16_lo(v[i].w) + bf16_hi(v[i].w));
#pragma unroll
    for (int o = 16; o > 0; o >>= 1) s += __shfl_xor_sync(0xffffffffu, s, o);
    const float mean = s * (1.0f / D_);
    float q = 0.f;
#pragma unroll
    for (int i = 0; i < 4; i++) {
      const uint32_t u[4] = {v[i].x, v[i].y, v[i].z, v[i].w};
#pragma unroll
      for (int e = 0; e < 4; e++) {
        const float d0 = bf16_lo(u[e]) - mean, d1 = bf16_hi(u[e]) - mean;
        q += d0 * d0; q += d1 * d1;
      }
    }
#pragma unroll
    for (int o = 16; o > 0; o >>= 1) q += __shfl_xor_sync(0xffffffffu, q, o);
    const float var = bf16r(q * (1.0f / D_));
    const uint32_t mb2 = pack_bf16(mean, mean);
    const float rden = 1.0f / bf16r(sqrtf(bf16r(var + 1e-5f)));
#pragma unroll
    for (int i = 0; i < 4; i++) {
      uint32_t u[4] = {v[i].x, v[i].y, v[i].z, v[i].w};
#pragma unroll
      for (int e = 0; e < 4; e++) {
        const uint32_t t = bsub2(u[e], mb2);
        u[e] = pack_bf16(bf16_lo(t) * rden, bf16_hi(t) * rden);
      }
      v[i] = make_uint4(u[0], u[1], u[2], u[3]);
    }
    {
      uint32_t a0, a1, a2, a3, g0, g1, g2, g3, it = 0;
      const uint2* src0 = g_modx + tid * 4;
      do {
        asm volatile("ld.volatile.global.v4.u32 {%0, %1, %2, %3}, [%4];" : "=r"(a0), "=r"(g0), "=r"(a1), "=r"(g1) : "l"(src0) : "memory");
        asm volatile("ld.volatile.global.v4.u32 {%0, %1, %2, %3}, [%4];" : "=r"(a2), "=r"(g2), "=r"(a3), "=r"(g3) : "l"(src0 + 2) : "memory");
        if (++it > (1u << 22)) __trap();
        if (g0 != tag || g1 != tag || g2 != tag || g3 != tag) __nanosleep(PRE_SLEEP);
      } while (g0 != tag || g1 != tag || g2 != tag || g3 != tag);
      *reinterpret_cast<uint2*>(s_mod + tid * 2) = make_uint2(__byte_perm(a0, a1, 0x7632), __byte_perm(a2, a3, 0x7632));
    }
    __syncthreads();
    TL(0, 1); TL(0, 2);
    bf16* orow = g_h + (size_t)row * D_;
#pragma unroll
    for (int i = 0; i < 4; i++) {
      const int cc0 = i * 256 + lane * 8;
      const uint4 sh = *reinterpret_cast<const uint4*>(s_mod + (cc0 >> 1)), sc = *reinterpret_cast<const uint4*>(s_mod + 512 + (cc0 >> 1));
      uint32_t o[4];
      o[0] = badd2(bmul2(v[i].x, sc.x), sh.x); o[1] = badd2(bmul2(v[i].y, sc.y), sh.y);
      o[2] = badd2(bmul2(v[i].z, sc.z), sh.z); o[3] = badd2(bmul2(v[i].w, sc.w), sh.w);
      *reinterpret_cast<uint4*>(orow + cc0) = make_uint4(o[0], o[1], o[2], o[3]);
    }
  } else {
#pragma unroll
    for (int p = 0; p < 2; p++) {
      const int r = kt * 64 + p * 32 + (ht >> 3), cc = (ht & 7) * 8;
      tv[p] = cc < 32 ? *reinterpret_cast<const uint4*>(wk + (size_t)r * 32 + cc)
                      : *reinterpret_cast<const uint4*>(wv + (size_t)r * 32 + (cc - 32));
    }
  }
  transpose();
  TL(0, 3);
}

__device__ __forceinline__ void mod_tail_gemv(const bf16* __restrict__ c, const bf16* __restrict__ wmod, int slab,
                                              float* __restrict__ smem_f) {
  float* s_c = smem_f;
  float* s_red = smem_f + 1024;
  const int tid = threadIdx.x;
  const int ct = tid & 127, rg = tid >> 7;
  const bf16* base = wmod + (size_t)(rg * 256) * 6144 + 2048 + slab * 1024 + ct * 8;
  uint4 wa[8], wb[8];
#pragma unroll
  for (int i = 0; i < 8; i++) wa[i] = __ldcs(reinterpret_cast<const uint4*>(base + (size_t)i * 6144));
  s_c[tid] = silu_bf16(__bfloat162float(c[tid]));
  s_c[tid + 512] = silu_bf16(__bfloat162float(c[tid + 512]));
  __syncthreads();
  float acc[8];
#pragma unroll
  for (int e = 0; e < 8; e++) acc[e] = 0.f;
  auto consume = [&](const uint4(&w)[8], int r0) {
#pragma unroll
    for (int i = 0; i < 8; i++) {
      const float cv = s_c[rg * 256 + r0 + i];
      acc[0] += cv * bf16_lo(w[i].x); acc[1] += cv * bf16_hi(w[i].x);
      acc[2] += cv * bf16_lo(w[i].y); acc[3] += cv * bf16_hi(w[i].y);
      acc[4] += cv * bf16_lo(w[i].z); acc[5] += cv * bf16_hi(w[i].z);
      acc[6] += cv * bf16_lo(w[i].w); acc[7] += cv * bf16_hi(w[i].w);
    }
  };
#pragma unroll 1
  for (int r0 = 0; r0 < 256; r0 += 16) {
#pragma unroll
    for (int i = 0; i < 8; i++) wb[i] = __ldcs(reinterpret_cast<const uint4*>(base + (size_t)(r0 + 8 + i) * 6144));
    consume(wa, r0);
    if (r0 + 16 < 256) {
#pragma unroll
      for (int i = 0; i < 8; i++) wa[i] = __ldcs(reinterpret_cast<const uint4*>(base + (size_t)(r0 + 16 + i) * 6144));
    }
    consume(wb, r0 + 8);
  }
  *reinterpret_cast<float4*>(s_red + rg * 1024 + ct * 8) = make_float4(acc[0], acc[1], acc[2], acc[3]);
  *reinterpret_cast<float4*>(s_red + rg * 1024 + ct * 8 + 4) = make_float4(acc[4], acc[5], acc[6], acc[7]);
  __syncthreads();
#pragma unroll
  for (int i = 0; i < 2; i++) {
    const int col = tid + i * 512;
    g_mod[2048 + slab * 1024 + col] = bf16r((s_red[col] + s_red[1024 + col]) + (s_red[2048 + col] + s_red[3072 + col]));
  }
}
__device__ __forceinline__ void l2_prefetch(const void* p, uint32_t bytes) {
  asm volatile("cp.async.bulk.prefetch.L2.global [%0], %1;" ::"l"(p), "r"(bytes) : "memory");
}

enum { EPI_QKV = 0, EPI_RES = 1, EPI_RELU = 2 };
#define FF1_EARLY 2
#define OUT_EARLY 8
#define FF2_EARLY 3
#define FF1_SPREAD 2
#define FF1_E0 0
#define FF1_E1 3
template <int BN, int BMODE, int KDIM, int NST, int EPI, int TPC>
struct GemmCfg {
  static constexpr int A_BYTES = 128 * 64 * 2;
  static constexpr int B_BYTES = BN * 64 * 2;
  static constexpr int STAGE = A_BYTES + B_BYTES;
  static constexpr int STG = EPI == EPI_RELU ? 32768 : 0;
  static constexpr int SMEM = NST * STAGE + STG + 1024 + 256 + 768;
};

__device__ __forceinline__ uint32_t res_pair(uint32_t x, uint32_t g2, float a0, float a1) {
  return badd2(x, bmul2(g2, pack_bf16(a0, a1)));
}
__device__ __forceinline__ uint32_t ln_pair(uint32_t x, uint32_t mb2, float rden, uint32_t sh2, uint32_t sc2) {
  const uint32_t t = bsub2(x, mb2);
  return badd2(bmul2(pack_bf16(bf16_lo(t) * rden, bf16_hi(t) * rden), sc2), sh2);
}
__device__ __align__(16) uint4 g_stat[S_ * 8];

template <int BN, int BMODE>
__device__ __forceinline__ void gemm_mma(float (&acc)[BN / 2], uint64_t da, uint64_t db, int scale_d) {
  if constexpr (BN == 136) wgmma_ss_n136_tb0(acc, da, db, scale_d);
  else if constexpr (BN == 128) wgmma_ss_n128_tb1(acc, da, db, scale_d);
  else wgmma_ss_n224_tb1(acc, da, db, scale_d);
}

template <int BN, int BMODE, int KDIM, int NST, int EPI, int TPC, int CM, int CN>
__global__ void __launch_bounds__(288, 1)
gemm_kernel(const __grid_constant__ CUtensorMap tmA, const __grid_constant__ CUtensorMap tmB,
            const __grid_constant__ CUtensorMap tmC, const __grid_constant__ CUtensorMap tmR,
            const __grid_constant__ CUtensorMap tmD, const float* __restrict__ gvec, const void* __restrict__ pf_ptr) {
  using Cfg = GemmCfg<BN, BMODE, KDIM, NST, EPI, TPC>;
  constexpr int KB = KDIM / 64;
  constexpr int CL = CM * CN;
  constexpr int NREL = CM + CN - 1;
  constexpr bool EARLY_B = (EPI != EPI_QKV);
  constexpr int EARLY_W = EPI == EPI_RELU ? FF1_EARLY : KDIM == 1024 ? OUT_EARLY : FF2_EARLY;
  constexpr int EARLY_N = EARLY_W < NST ? EARLY_W : NST;
  constexpr bool LNF = (EPI == EPI_RES && KDIM == 1024);
  static_assert(BMODE != 0 || CM == 1, "K-major B is not split");
  extern __shared__ __align__(1024) uint8_t smem_raw[];
  const uint32_t sbase = (smem_u32(smem_raw) + 1023u) & ~1023u;
  const uint32_t stg = sbase + (EPI == EPI_RELU ? NST : EPI == EPI_RES ? KB % NST : 0) * Cfg::STAGE;
  const uint32_t bars = sbase + NST * Cfg::STAGE + Cfg::STG;
  const uint32_t bar_full = bars, bar_empty = bars + 8 * NST;
  const int warp = threadIdx.x >> 5, lane = threadIdx.x & 31;
  constexpr int TLID = EPI == EPI_QKV ? 1 : EPI == EPI_RELU ? 5 : KDIM == 1024 ? 3 : 6;
  TL(TLID, 0);

  if (threadIdx.x == 0) {
    for (int i = 0; i < NST; i++) { mbar_init(bar_full + 8 * i, 1); mbar_init(bar_empty + 8 * i, 8 * NREL); }
    fence_mbar_init();
  }
  if (threadIdx.x == 256) {
    prefetch_tmap(&tmA); prefetch_tmap(&tmB); prefetch_tmap(&tmC);
    if (EPI == EPI_RES) prefetch_tmap(&tmR);
    if (LNF) prefetch_tmap(&tmD);
  }
  if constexpr (CL > 1) { cluster_arrive(); cluster_wait(); } else { __syncthreads(); }

  const int rank = CL > 1 ? (int)cluster_ctarank() : 0;
  const int cm = rank / CN, cn = rank % CN;
  const int cid = blockIdx.x / CL;
  const int tm = (cid / (8 / CN)) * CM + cm, tn0 = (cid % (8 / CN)) * CN + cn;
  const uint16_t maskA = (uint16_t)(((1u << CN) - 1u) << (cm * CN));
  uint16_t maskB = 0;
#pragma unroll
  for (int i = 0; i < CM; i++) maskB |= (uint16_t)(1u << (i * CN + cn));

  auto load_a = [&](int st, int kb) {
    const uint32_t sa = sbase + st * Cfg::STAGE;
    if constexpr (CN == 1) tma_load_2d(sa, &tmA, bar_full + 8 * st, kb * 64, tm * 128);
    else tma_load_2d_mc(sa + cn * (16384 / CN), &tmA, bar_full + 8 * st, kb * 64, tm * 128 + cn * (128 / CN), maskA);
  };
  auto load_b = [&](int st, int kb, int tn) {
    const uint32_t sb = sbase + st * Cfg::STAGE + Cfg::A_BYTES;
    if constexpr (BMODE == 0) tma_load_2d(sb, &tmB, bar_full + 8 * st, kb * 64, tn * BN);
    else if constexpr (BMODE == 1) {
      if constexpr (CM == 1) tma_load_3d(sb, &tmB, bar_full + 8 * st, 0, kb * 64, tn * 2);
      else if constexpr (CM == 2) tma_load_3d_mc(sb + cm * 8192, &tmB, bar_full + 8 * st, 0, kb * 64, tn * 2 + cm, maskB);
      else tma_load_3d_mc(sb + cm * 4096, &tmB, bar_full + 8 * st, 0, kb * 64 + (cm & 1) * 32, tn * 2 + (cm >> 1), maskB);
    } else {
      if constexpr (CM == 1) tma_load_3d(sb, &tmB, bar_full + 8 * st, 0, kb * 64, tn * (BN / 32));
      else tma_load_3d_mc(sb + cm * (Cfg::B_BYTES / 2), &tmB, bar_full + 8 * st, 0, kb * 64 + cm * 32, tn * (BN / 32), maskB);
    }
  };

  if (EARLY_B && threadIdx.x == 256) {
#pragma unroll 1
    for (int s = 0; s < EARLY_N; s++) { mbar_expect_tx(bar_full + 8 * s, Cfg::STAGE); load_b(s, s, tn0); }
  }
  pdl_wait();
  pdl_launch();
  TL(TLID, 1); TL(TLID, 2);
  if (EPI == EPI_QKV && blockIdx.x == 0 && threadIdx.x == 64) g_epoch = g_epoch + 1u;

  if (warp >= 8) {
    if (warp == 8 && lane == 0) {
      int st = 0; uint32_t ph = 0;
      for (int it = 0; it < TPC; it++) {
        const int tn = it * 8 + tn0;
        for (int kb = 0; kb < KB; kb++) {
          if (EARLY_B && it == 0 && kb < EARLY_N) {
            load_a(st, kb);
          } else {
            mbar_wait(bar_empty + 8 * st, ph ^ 1);
            mbar_expect_tx(bar_full + 8 * st, Cfg::STAGE);
            load_a(st, kb);
            load_b(st, kb, tn);
          }
          if (EPI == EPI_RELU && it == 0 && kb >= 2) {
            l2_prefetch(reinterpret_cast<const uint8_t*>(pf_ptr) + (size_t)blockIdx.x * 57344 + (kb - 2) * 4096, 4096);
          }
          if (++st == NST) { st = 0; ph ^= 1; }
        }
      }
      if constexpr (EPI == EPI_RES) {
        mbar_wait(bar_empty + 8 * st, ph ^ 1);
        mbar_expect_tx(bar_full + 8 * st, 32768);
#pragma unroll
        for (int w = 0; w < 2; w++)
#pragma unroll
          for (int cch = 0; cch < 2; cch++)
            tma_load_2d(stg + (w * 2 + cch) * 8192, &tmR, bar_full + 8 * st, tn0 * 128 + cch * 64, tm * 128 + w * 64);
      }
    }
    __syncwarp();
    if constexpr (CL > 1) { cluster_arrive(); cluster_wait(); }
    return;
  } else {
    const int wg = warp >> 2, wq4 = warp & 3;
    const int g = lane >> 2, t4 = lane & 3;
    int st = 0; uint32_t ph = 0;
    uint32_t rel_addr = bar_empty;
    if constexpr (CL > 1) {
      int tr = cm * CN + lane;
      if (lane >= CN) { const int j = lane - CN; tr = (j >= cm ? j + 1 : j) * CN + cn; }
      rel_addr = mapa_u32(bar_empty, lane < NREL ? tr : rank);
    }
    auto release = [&](int s) {
      if constexpr (CL > 1) { if (lane < NREL) mbar_arrive_cluster(rel_addr + 8 * s); }
      else { if (lane == 0) mbar_arrive(bar_empty + 8 * s); }
    };
    unsigned int tag = 0;
    if constexpr (EPI == EPI_RES) {
      if (threadIdx.x < 64) {
        const float2 gv = __ldcg(reinterpret_cast<const float2*>(gvec + tn0 * 128) + threadIdx.x);
        asm volatile("st.shared.u32 [%0], %1;" ::"r"(bars + 256 + threadIdx.x * 4), "r"(pack_bf16(gv.x, gv.y)) : "memory");
      } else if (LNF && threadIdx.x < 128) {
        const int ci = threadIdx.x - 64;
        const float2 sh = __ldcg(reinterpret_cast<const float2*>(gvec + 1024 + tn0 * 128) + ci);
        const float2 sc = __ldcg(reinterpret_cast<const float2*>(gvec + 2048 + tn0 * 128) + ci);
        asm volatile("st.shared.v2.u32 [%0], {%1, %2};" ::"r"(bars + 512 + ci * 8), "r"(pack_bf16(sh.x, sh.y)),
                     "r"(pack_bf16(1.0f + sc.x, 1.0f + sc.y)) : "memory");
      }
      if constexpr (LNF) asm volatile("ld.volatile.global.u32 %0, [%1];" : "=r"(tag) : "l"(&g_epoch) : "memory");
    }
    uint32_t pk[EPI == EPI_RELU ? 24 : 1];
    const uint32_t erow = (wq4 * 16 + (lane & 7) + ((lane >> 3) & 1) * 8) * 64;
    const uint32_t esw = (uint32_t)(((lane & 7) >> 1) & 3);
    auto relu_addr = [&](uint32_t base, int jj) {
      const int cg = jj + (lane >> 4);
      return base + (cg >> 2) * 4096 + erow + (((cg & 3) ^ esw) << 4);
    };
    auto relu_flush = [&](int c0, int nch, uint32_t base, int tnp) {
      fence_proxy_async();
      named_bar_sync(1 + wg, 128);
      if (wq4 == 0 && lane == 0) {
        for (int cch = 0; cch < nch; cch++)
          tma_store_2d(&tmC, base + cch * 4096, tnp * BN + (c0 + cch) * 32, tm * 128 + wg * 64);
        bulk_commit();
      }
    };
#pragma unroll
    for (int it = 0; it < TPC; it++) {
      const int tn = it * 8 + tn0;
      float acc[BN / 2];
      int prev_st = 0;
      for (int kb = 0; kb < KB; kb++) {
        mbar_wait(bar_full + 8 * st, ph);
        const uint32_t sa = sbase + st * Cfg::STAGE + wg * 8192, sb = sbase + st * Cfg::STAGE + Cfg::A_BYTES;
        wgmma_fence();
#pragma unroll
        for (int k = 0; k < 4; k++) {
          const uint64_t da = make_desc(sa + k * 32, 16, 1024, 1);
          uint64_t db;
          if (BMODE == 0) db = make_desc(sb + k * 32, 16, 1024, 1);
          else if (BMODE == 1) db = make_desc(sb + k * 2048, 8192, 1024, 1);
          else if (CM == 1) db = make_desc(sb + k * 1024, 4096, 512, 2);
          else db = make_desc(sb + (k >> 1) * (Cfg::B_BYTES / 2) + (k & 1) * 1024, 2048, 512, 2);
          gemm_mma<BN, BMODE>(acc, da, db, (kb > 0 || k > 0) ? 1 : 0);
        }
        wgmma_commit();
        if constexpr (EPI == EPI_RELU) {
          constexpr int SP = FF1_SPREAD, E1 = 4 * SP + (SP == 1), E2 = E1 + 3 * SP + 1;
          if (it > 0) {
            if (kb == 0) { fence_proxy_async(); named_bar_sync(1 + wg, 128); }
            if (kb == E1) {
              if (wq4 == 0 && lane == 0) bulk_wait_read0();
              named_bar_sync(1 + wg, 128);
#pragma unroll
              for (int jj = 0; jj < 12; jj += 2)
                stmatrix_x4(relu_addr(stg + wg * 16384, jj), pk[2 * jj], pk[2 * jj + 1], pk[2 * jj + 2], pk[2 * jj + 3]);
              fence_proxy_async();
              named_bar_sync(1 + wg, 128);
            }
            if (wq4 == 0 && lane == 0) {
              const int r = kb >= E1 ? kb - E1 : kb, slot = r / SP;
              if (r % SP == 0 && slot < (kb >= E1 ? 3 : 4)) {
                tma_store_2d(&tmC, stg + wg * 16384 + slot * 4096, (tn - 8) * BN + ((kb >= E1 ? 4 : 0) + slot) * 32, tm * 128 + wg * 64);
                bulk_commit();
              }
            }
            if (kb == E2) {
              if (wq4 == 0 && lane == 0) bulk_wait_read0();
              named_bar_sync(1 + wg, 128);
            }
          }
        }
        if (kb > 0) {
          wgmma_wait<1>();
          release(prev_st);
        }
        prev_st = st;
        if (++st == NST) { st = 0; ph ^= 1; }
      }
      wgmma_wait<0>();
      release(prev_st);
      if constexpr (CL > 1) { if (it == TPC - 1) { __syncwarp(); cluster_arrive(); } }

      const int mrow = wq4 * 16 + (lane & 7) + ((lane >> 3) & 1) * 8;
      const int mcol = lane >> 4;
      if constexpr (LNF) {
        const uint32_t wbase = stg + wg * 16384;
        named_bar_sync(3, 256);
        mbar_wait(bar_full + 8 * st, ph);
        uint32_t xr[32];
        float s0 = 0.f, s1 = 0.f;
#pragma unroll
        for (int j = 0; j < 16; j += 2) {
          const int cg = j + mcol;
          const uint32_t addr = wbase + (cg >> 3) * 8192 + mrow * 128 + (((cg & 7) ^ (mrow & 7)) << 4);
          uint32_t x0, x1, x2, x3;
          ldmatrix_x4(addr, x0, x1, x2, x3);
          uint32_t ga, gb;
          asm volatile("ld.shared.u32 %0, [%1];" : "=r"(ga) : "r"(bars + 256 + (j * 4 + t4) * 4));
          asm volatile("ld.shared.u32 %0, [%1];" : "=r"(gb) : "r"(bars + 256 + (j * 4 + 4 + t4) * 4));
          xr[2 * j + 0] = res_pair(x0, ga, acc[4 * j + 0], acc[4 * j + 1]);
          xr[2 * j + 1] = res_pair(x1, ga, acc[4 * j + 2], acc[4 * j + 3]);
          xr[2 * j + 2] = res_pair(x2, gb, acc[4 * j + 4], acc[4 * j + 5]);
          xr[2 * j + 3] = res_pair(x3, gb, acc[4 * j + 6], acc[4 * j + 7]);
          s0 += (bf16_lo(xr[2 * j]) + bf16_hi(xr[2 * j])) + (bf16_lo(xr[2 * j + 2]) + bf16_hi(xr[2 * j + 2]));
          s1 += (bf16_lo(xr[2 * j + 1]) + bf16_hi(xr[2 * j + 1])) + (bf16_lo(xr[2 * j + 3]) + bf16_hi(xr[2 * j + 3]));
        }
        s0 += __shfl_xor_sync(0xffffffffu, s0, 1); s0 += __shfl_xor_sync(0xffffffffu, s0, 2);
        s1 += __shfl_xor_sync(0xffffffffu, s1, 1); s1 += __shfl_xor_sync(0xffffffffu, s1, 2);
        const float lm0 = s0 * (1.0f / 128.0f), lm1 = s1 * (1.0f / 128.0f);
        float q0 = 0.f, q1 = 0.f;
#pragma unroll
        for (int i = 0; i < 32; i += 2) {
          const float a0 = bf16_lo(xr[i]) - lm0, a1 = bf16_hi(xr[i]) - lm0, b0 = bf16_lo(xr[i + 1]) - lm1, b1 = bf16_hi(xr[i + 1]) - lm1;
          q0 += a0 * a0; q0 += a1 * a1; q1 += b0 * b0; q1 += b1 * b1;
        }
        q0 += __shfl_xor_sync(0xffffffffu, q0, 1); q0 += __shfl_xor_sync(0xffffffffu, q0, 2);
        q1 += __shfl_xor_sync(0xffffffffu, q1, 1); q1 += __shfl_xor_sync(0xffffffffu, q1, 2);
        if (t4 < 2) {
          asm volatile("st.volatile.global.v4.u32 [%0], {%1, %2, %3, %4};" ::"l"(g_stat + ((tm * 8 + warp) * 8 + tn) * 16 + g + t4 * 8),
                       "r"(__float_as_uint(t4 ? lm1 : lm0)), "r"(tag), "r"(__float_as_uint(t4 ? q1 : q0)), "r"(tag)
                       : "memory");
        }
#pragma unroll
        for (int j = 0; j < 16; j += 2) {
          const int cg = j + mcol;
          const uint32_t addr = wbase + (cg >> 3) * 8192 + mrow * 128 + (((cg & 7) ^ (mrow & 7)) << 4);
          stmatrix_x4(addr, xr[2 * j], xr[2 * j + 1], xr[2 * j + 2], xr[2 * j + 3]);
        }
        fence_proxy_async();
        named_bar_sync(1 + wg, 128);
        if (wq4 == 0 && lane == 0) {
          tma_store_2d(&tmC, wbase, tn * 128, tm * 128 + wg * 64);
          tma_store_2d(&tmC, wbase + 8192, tn * 128 + 64, tm * 128 + wg * 64);
          bulk_commit();
        }
        uint4 e00, e01, e10, e11;
        {
          const uint4* p0 = g_stat + ((tm * 8 + warp) * 8 + t4 * 2) * 16 + g;
          const uint4* p1 = p0 + 8;
          uint32_t itn = 0;
          bool done;
          do {
            asm volatile("ld.volatile.global.v4.u32 {%0, %1, %2, %3}, [%4];" : "=r"(e00.x), "=r"(e00.y), "=r"(e00.z), "=r"(e00.w) : "l"(p0) : "memory");
            asm volatile("ld.volatile.global.v4.u32 {%0, %1, %2, %3}, [%4];" : "=r"(e01.x), "=r"(e01.y), "=r"(e01.z), "=r"(e01.w) : "l"(p0 + 16) : "memory");
            asm volatile("ld.volatile.global.v4.u32 {%0, %1, %2, %3}, [%4];" : "=r"(e10.x), "=r"(e10.y), "=r"(e10.z), "=r"(e10.w) : "l"(p1) : "memory");
            asm volatile("ld.volatile.global.v4.u32 {%0, %1, %2, %3}, [%4];" : "=r"(e11.x), "=r"(e11.y), "=r"(e11.z), "=r"(e11.w) : "l"(p1 + 16) : "memory");
            done = e00.y == tag && e00.w == tag && e01.y == tag && e01.w == tag && e10.y == tag && e10.w == tag &&
                   e11.y == tag && e11.w == tag;
            if (++itn > (1u << 22)) __trap();
            if (!done) __nanosleep(50);
          } while (!done);
        }
        __syncwarp();
        float m0 = __uint_as_float(e00.x) + __uint_as_float(e01.x), m1 = __uint_as_float(e10.x) + __uint_as_float(e11.x);
        m0 += __shfl_xor_sync(0xffffffffu, m0, 1); m0 += __shfl_xor_sync(0xffffffffu, m0, 2);
        m1 += __shfl_xor_sync(0xffffffffu, m1, 1); m1 += __shfl_xor_sync(0xffffffffu, m1, 2);
        m0 *= 0.125f; m1 *= 0.125f;
        const float d00 = __uint_as_float(e00.x) - m0, d01 = __uint_as_float(e01.x) - m0;
        const float d10 = __uint_as_float(e10.x) - m1, d11 = __uint_as_float(e11.x) - m1;
        float v0 = (__uint_as_float(e00.z) + __uint_as_float(e01.z)) + 128.0f * (d00 * d00 + d01 * d01);
        float v1 = (__uint_as_float(e10.z) + __uint_as_float(e11.z)) + 128.0f * (d10 * d10 + d11 * d11);
        v0 += __shfl_xor_sync(0xffffffffu, v0, 1); v0 += __shfl_xor_sync(0xffffffffu, v0, 2);
        v1 += __shfl_xor_sync(0xffffffffu, v1, 1); v1 += __shfl_xor_sync(0xffffffffu, v1, 2);
        const uint32_t mb0 = pack_bf16(m0, m0), mb1 = pack_bf16(m1, m1);
        const float rd0 = 1.0f / bf16r(sqrtf(bf16r(bf16r(v0 * (1.0f / D_)) + 1e-5f)));
        const float rd1 = 1.0f / bf16r(sqrtf(bf16r(bf16r(v1 * (1.0f / D_)) + 1e-5f)));
        const uint32_t hbase = sbase + ((KB + 1) % NST) * Cfg::STAGE + wg * 16384;
#pragma unroll
        for (int hf = 0; hf < 2; hf++) {
#pragma unroll
          for (int j = hf * 8; j < hf * 8 + 8; j += 2) {
            const int cg = j + mcol;
            const uint32_t addr = hbase + (cg >> 3) * 8192 + mrow * 128 + (((cg & 7) ^ (mrow & 7)) << 4);
            uint2 va, vb;
            asm volatile("ld.shared.v2.u32 {%0, %1}, [%2];" : "=r"(va.x), "=r"(va.y) : "r"(bars + 512 + (j * 4 + t4) * 8));
            asm volatile("ld.shared.v2.u32 {%0, %1}, [%2];" : "=r"(vb.x), "=r"(vb.y) : "r"(bars + 512 + (j * 4 + 4 + t4) * 8));
            stmatrix_x4(addr, ln_pair(xr[2 * j], mb0, rd0, va.x, va.y), ln_pair(xr[2 * j + 1], mb1, rd1, va.x, va.y),
                        ln_pair(xr[2 * j + 2], mb0, rd0, vb.x, vb.y), ln_pair(xr[2 * j + 3], mb1, rd1, vb.x, vb.y));
          }
          fence_proxy_async();
          named_bar_sync(1 + wg, 128);
          if (wq4 == 0 && lane == 0) {
            tma_store_2d(&tmD, hbase + hf * 8192, tn * 128 + hf * 64, tm * 128 + wg * 64);
            bulk_commit();
          }
        }
        if (wq4 == 0 && lane == 0) bulk_wait_read0();
      } else if constexpr (EPI == EPI_QKV || EPI == EPI_RES) {
        const uint32_t wbase = stg + wg * 16384;
        named_bar_sync(3, 256);
        if (EPI == EPI_RES) mbar_wait(bar_full + 8 * st, ph);
#pragma unroll
        for (int hf = 0; hf < 2; hf++) {
#pragma unroll
        for (int j = hf * 8; j < hf * 8 + 8; j += 2) {
          const int cg = j + mcol;
          const uint32_t addr = wbase + (cg >> 3) * 8192 + mrow * 128 + (((cg & 7) ^ (mrow & 7)) << 4);
          uint32_t r0, r1, r2, r3;
          if constexpr (EPI == EPI_RES) {
            uint32_t x0, x1, x2, x3;
            ldmatrix_x4(addr, x0, x1, x2, x3);
            uint32_t ga, gb;
            asm volatile("ld.shared.u32 %0, [%1];" : "=r"(ga) : "r"(bars + 256 + (j * 4 + t4) * 4));
            asm volatile("ld.shared.u32 %0, [%1];" : "=r"(gb) : "r"(bars + 256 + (j * 4 + 4 + t4) * 4));
            r0 = res_pair(x0, ga, acc[4 * j + 0], acc[4 * j + 1]);
            r1 = res_pair(x1, ga, acc[4 * j + 2], acc[4 * j + 3]);
            r2 = res_pair(x2, gb, acc[4 * j + 4], acc[4 * j + 5]);
            r3 = res_pair(x3, gb, acc[4 * j + 6], acc[4 * j + 7]);
          } else {
            r0 = pack_bf16(acc[4 * j + 0], acc[4 * j + 1]);
            r1 = pack_bf16(acc[4 * j + 2], acc[4 * j + 3]);
            r2 = pack_bf16(acc[4 * j + 4], acc[4 * j + 5]);
            r3 = pack_bf16(acc[4 * j + 6], acc[4 * j + 7]);
          }
          stmatrix_x4(addr, r0, r1, r2, r3);
        }
        fence_proxy_async();
        named_bar_sync(1 + wg, 128);
        if (wq4 == 0 && lane == 0) {
          tma_store_2d(&tmC, wbase + hf * 8192, tn * 128 + hf * 64, tm * 128 + wg * 64);
          bulk_commit();
        }
        }
        if constexpr (EPI == EPI_QKV) {
          const int r0g = tm * 128 + wg * 64 + wq4 * 16 + g;
          if (tn < 4) {
            *reinterpret_cast<uint32_t*>(g_k + (size_t)r0g * 32 + tn * 8 + t4 * 2) = pack_bf16(acc[64], acc[65]);
            *reinterpret_cast<uint32_t*>(g_k + (size_t)(r0g + 8) * 32 + tn * 8 + t4 * 2) = pack_bf16(acc[66], acc[67]);
          } else {
            const int d0 = (tn - 4) * 8 + t4 * 2;
            g_vT[(size_t)d0 * S_ + r0g] = __float2bfloat16_rn(acc[64]);
            g_vT[(size_t)(d0 + 1) * S_ + r0g] = __float2bfloat16_rn(acc[65]);
            g_vT[(size_t)d0 * S_ + r0g + 8] = __float2bfloat16_rn(acc[66]);
            g_vT[(size_t)(d0 + 1) * S_ + r0g + 8] = __float2bfloat16_rn(acc[67]);
          }
        }
        if (wq4 == 0 && lane == 0) bulk_wait_read0();
      } else {
        static_assert(EPI != EPI_RELU || TPC <= 2, "staging reuse assumes at most two tiles");
        auto stage_acc = [&](int c0, int nch, uint32_t base) {
#pragma unroll
          for (int jj = 0; jj < 16; jj += 2) {
            if (jj < nch * 4) {
              const int j = c0 * 4 + jj;
              stmatrix_x4(relu_addr(base, jj), pack_bf16_relu(acc[4 * j + 0], acc[4 * j + 1]), pack_bf16_relu(acc[4 * j + 2], acc[4 * j + 3]),
                          pack_bf16_relu(acc[4 * j + 4], acc[4 * j + 5]), pack_bf16_relu(acc[4 * j + 6], acc[4 * j + 7]));
            }
          }
        };
        if (it < TPC - 1) {
          stage_acc(0, 4, stg + wg * 16384);
#pragma unroll
          for (int i = 0; i < 24; i++) pk[i] = pack_bf16_relu(acc[64 + 2 * i], acc[64 + 2 * i + 1]);
        } else {
          stage_acc(0, 2, stg + wg * 16384);
          relu_flush(0, 2, stg + wg * 16384, tn);
          stage_acc(2, 2, stg + wg * 16384 + 8192);
          relu_flush(2, 2, stg + wg * 16384 + 8192, tn);
          stage_acc(4, 2, sbase + wg * 8192);
          stage_acc(6, 1, sbase + Cfg::STAGE + wg * 8192);
          fence_proxy_async();
          named_bar_sync(1 + wg, 128);
          if (wq4 == 0 && lane == 0) {
            tma_store_2d(&tmC, sbase + wg * 8192, tn * BN + 128, tm * 128 + wg * 64);
            tma_store_2d(&tmC, sbase + wg * 8192 + 4096, tn * BN + 160, tm * 128 + wg * 64);
            tma_store_2d(&tmC, sbase + Cfg::STAGE + wg * 8192, tn * BN + 192, tm * 128 + wg * 64);
            bulk_commit();
          }
        }
        if (it == TPC - 1 && wq4 == 0 && lane == 0) bulk_wait_read0();
      }
    }
  }
  if constexpr (CL > 1) { __syncwarp(); cluster_wait(); }
  TL(TLID, 3);
}

constexpr int ATT_NST = 4;
constexpr int ATT_STAGE = 8192 + 2 * 5120;
constexpr int ATT_SMEM = ATT_NST * ATT_STAGE + 256;
#define ATT_PVSPLIT 8
constexpr int ATT_KBOX = 128, ATT_GRID = 132, ATT_THREADS = 512;
constexpr float ATT_SC = 0.17677669529663687f * 1.4426950408889634f;

__device__ __noinline__ void attn_slow_row(const bf16* __restrict__ q, bf16* __restrict__ o, int row, int lane) {
  float qv[32];
#pragma unroll
  for (int d = 0; d < 32; d++) qv[d] = __bfloat162float(q[(size_t)row * 32 + d]);
  float m = -INFINITY;
  for (int j = lane; j < S_; j += 32) {
    float s = 0.f;
#pragma unroll
    for (int d = 0; d < 32; d++) s += qv[d] * __bfloat162float(g_k[(size_t)j * 32 + d]);
    m = fmaxf(m, s);
  }
#pragma unroll
  for (int of = 16; of > 0; of >>= 1) m = fmaxf(m, __shfl_xor_sync(0xffffffffu, m, of));
  float acc[32];
#pragma unroll
  for (int d = 0; d < 32; d++) acc[d] = 0.f;
  float sum = 0.f;
  for (int j = lane; j < S_; j += 32) {
    float s = 0.f;
#pragma unroll
    for (int d = 0; d < 32; d++) s += qv[d] * __bfloat162float(g_k[(size_t)j * 32 + d]);
    const float p = exp2f((s - m) * ATT_SC);
    sum += p;
#pragma unroll
    for (int d = 0; d < 32; d++) acc[d] += p * __bfloat162float(g_vT[(size_t)d * S_ + j]);
  }
#pragma unroll
  for (int of = 16; of > 0; of >>= 1) sum += __shfl_xor_sync(0xffffffffu, sum, of);
  float mine = 0.f;
#pragma unroll
  for (int d = 0; d < 32; d++) {
    float a = acc[d];
#pragma unroll
    for (int of = 16; of > 0; of >>= 1) a += __shfl_xor_sync(0xffffffffu, a, of);
    if (lane == d) mine = a;
  }
  o[(size_t)row * 32 + lane] = __float2bfloat16_rn(mine / sum);
}

__device__ __forceinline__ float ex2(float x) {
  float y;
  asm volatile("ex2.approx.ftz.f32 %0, %1;" : "=f"(y) : "f"(x));
  return y;
}

constexpr float EX2_C0 = 0.999928057f, EX2_C1 = 0.693260968f, EX2_C2 = 0.242611125f, EX2_C3 = 0.0551716685f;
__device__ __forceinline__ float ex2_fma(float s, float zb) {
  float z;
  asm("fma.rn.sat.f32 %0, %1, %2, %3;" : "=f"(z) : "f"(s), "f"(ATT_SC / 253.0f), "f"(zb));
  const float t = fmaf(z, 253.0f, 12582912.0f - 125.0f);
  const float w = t - (12582912.0f - 125.0f);
  const float f = fmaf(z, 253.0f, -w);
  const float p = fmaf(fmaf(fmaf(EX2_C3, f, EX2_C2), f, EX2_C1), f, EX2_C0);
  return __uint_as_float(__float_as_uint(p) + (__float_as_uint(t) << 23));
}
#define ATT_NPOLY 12
__host__ __device__ constexpr bool att_is_poly(int i) { return ((i + 1) * ATT_NPOLY) / 64 != (i * ATT_NPOLY) / 64; }

constexpr uint32_t ATT_BARS = ATT_NST * ATT_STAGE;

__device__ __forceinline__ void attn_issue_load(uint32_t sbase, const CUtensorMap* tmK, const CUtensorMap* tmV, int st, int j) {
  const uint32_t sk = sbase + st * ATT_STAGE, bar = sbase + ATT_BARS + 8 * st;
  mbar_expect_tx(bar, 16384);
  tma_load_2d(sk, tmK, bar, 0, j * 128);
  tma_load_2d(sk + 8192, tmV, bar, j * 128, 0);
  tma_load_2d(sk + 8192 + 5120, tmV, bar, j * 128 + 64, 0);
}

__device__ __forceinline__ uint64_t desc_at(uint32_t dlo, uint32_t byte_off, uint32_t hi) {
  uint64_t d;
  asm("mov.b64 %0, {%1, %2};" : "=l"(d) : "r"(dlo + (byte_off >> 4)), "r"(hi));
  return d;
}
template <int ST>
__device__ __forceinline__ void attn_tile(const uint32_t sbase, const CUtensorMap* tmK, const CUtensorMap* tmV, const int outer,
                                          const int warp, const bool lane0, const uint32_t (&qa)[8], float (&oacc)[20],
                                          float& nm0, float& nm1, float& zb0, float& zb1) {
  const uint32_t ph = outer & 1;
  if (warp == ST * 4 + 1) {
    const int L = outer * 4 + ST + 2;
    if (lane0 && L < 32) {
      constexpr int LS = (ST + 2) & 3;
      mbar_wait(sbase + ATT_BARS + 8 * ATT_NST + 8 * LS, ST < 2 ? (ph ^ 1) : ph);
      attn_issue_load(sbase, tmK, tmV, LS, L & 15);
    }
    __syncwarp();
  }
  mbar_wait(sbase + ATT_BARS + 8 * ST, ph);
  const uint32_t dlo = (sbase >> 4) | 0x10000u;
  float s[64];
  wgmma_fence();
  wgmma_rs_n128_tb0(s, qa[0], qa[1], qa[2], qa[3], desc_at(dlo, ST * ATT_STAGE, 0x80000020u), 0);
  wgmma_rs_n128_tb0(s, qa[4], qa[5], qa[6], qa[7], desc_at(dlo, ST * ATT_STAGE + 32, 0x80000020u), 1);
  wgmma_commit();
  wgmma_wait<0>();
  if (ST == 0 && (outer & 3) == 0) {
    float m0 = s[0], m1 = s[2];
#pragma unroll
    for (int i = 0; i < 16; i++) {
      m0 = fmaxf(m0, fmaxf(s[4 * i], s[4 * i + 1]));
      m1 = fmaxf(m1, fmaxf(s[4 * i + 2], s[4 * i + 3]));
    }
    m0 = fmaxf(m0, __shfl_xor_sync(0xffffffffu, m0, 1)); m0 = fmaxf(m0, __shfl_xor_sync(0xffffffffu, m0, 2));
    m1 = fmaxf(m1, __shfl_xor_sync(0xffffffffu, m1, 1)); m1 = fmaxf(m1, __shfl_xor_sync(0xffffffffu, m1, 2));
    nm0 = -(m0 * ATT_SC + 64.f);
    nm1 = -(m1 * ATT_SC + 64.f);
    zb0 = (nm0 + 125.f) * (1.0f / 253.0f);
    zb1 = (nm1 + 125.f) * (1.0f / 253.0f);
  }
  uint32_t p[32];
#pragma unroll
  for (int h = 0; h < ATT_PVSPLIT; h++) {
#pragma unroll
    for (int i = h * (16 / ATT_PVSPLIT); i < (h + 1) * (16 / ATT_PVSPLIT); i++) {
      const float e0 = att_is_poly(4 * i) ? ex2_fma(s[4 * i], zb0) : ex2(fmaf(s[4 * i], ATT_SC, nm0));
      const float e1 = att_is_poly(4 * i + 1) ? ex2_fma(s[4 * i + 1], zb0) : ex2(fmaf(s[4 * i + 1], ATT_SC, nm0));
      const float e2 = att_is_poly(4 * i + 2) ? ex2_fma(s[4 * i + 2], zb1) : ex2(fmaf(s[4 * i + 2], ATT_SC, nm1));
      const float e3 = att_is_poly(4 * i + 3) ? ex2_fma(s[4 * i + 3], zb1) : ex2(fmaf(s[4 * i + 3], ATT_SC, nm1));
      p[2 * i] = pack_bf16(e0, e1);
      p[2 * i + 1] = pack_bf16(e2, e3);
    }
    wgmma_fence();
#pragma unroll
    for (int kk = h * (8 / ATT_PVSPLIT); kk < (h + 1) * (8 / ATT_PVSPLIT); kk++) {
      const uint32_t va = ST * ATT_STAGE + 8192 + (kk >> 2) * 5120 + (kk & 3) * 32;
      wgmma_rs_n40_tb0(oacc, p[4 * kk], p[4 * kk + 1], p[4 * kk + 2], p[4 * kk + 3], desc_at(dlo, va, 0x40000040u), 1);
    }
  }
  wgmma_commit();
  wgmma_wait<0>();
  if (lane0) mbar_arrive(sbase + ATT_BARS + 8 * ATT_NST + 8 * ST);
}

__global__ void __launch_bounds__(512, 1)
attn_kernel(const __grid_constant__ CUtensorMap tmK, const __grid_constant__ CUtensorMap tmV,
            const bf16* __restrict__ q, bf16* __restrict__ o, const bf16* __restrict__ cvec,
            const bf16* __restrict__ wmod, const bf16* __restrict__ wo, const bf16* __restrict__ w1) {
  extern __shared__ __align__(1024) uint8_t smem_raw[];
  if (blockIdx.x < 4) {
    pdl_launch();
    TL(7, 0); TL(7, 1); TL(7, 2);
    mod_tail_gemv(cvec, wmod, blockIdx.x, reinterpret_cast<float*>(smem_raw));
    TL(7, 3);
    return;
  }
  const int bid = blockIdx.x - 4;
  TL(2, 0);
  uint32_t sbase;
  asm("mov.u32 %0, smem_raw;" : "=r"(sbase));
  if (sbase & 1023u) __trap();
  const int warp = threadIdx.x >> 5, lane = threadIdx.x & 31;

  if (threadIdx.x == 0) {
    for (int i = 0; i < ATT_NST; i++) { mbar_init(sbase + ATT_BARS + 8 * i, 1); mbar_init(sbase + ATT_BARS + 8 * ATT_NST + 8 * i, 16); }
    fence_mbar_init();
  }
  if (threadIdx.x == 32) { prefetch_tmap(&tmK); prefetch_tmap(&tmV); }
  for (int i = threadIdx.x; i < ATT_NST * 2 * 256; i += 512) {
    const int stc = i >> 8, w = i & 255;
    uint32_t* p = reinterpret_cast<uint32_t*>(smem_raw + (stc >> 1) * ATT_STAGE + 8192 + (stc & 1) * 5120 + 4096) + w;
    *p = (w < 32) ? 0x3F803F80u : 0u;
  }
  fence_proxy_async();
  __syncthreads();
  pdl_wait();
  pdl_launch();
  TL(2, 1); TL(2, 2);

  if (threadIdx.x == 0) {
    attn_issue_load(sbase, &tmK, &tmV, 0, 0);
    attn_issue_load(sbase, &tmK, &tmV, 1, 1);
  }
  if (lane < 8)
    asm volatile("prefetch.global.L1 [%0];" ::"l"(q + (size_t)((bid * 8 + 4) * 64 + warp * 16) * 32 + lane * 64) : "memory");
  __syncwarp();
  const bool lane0 = lane == 0;
  const int g = lane >> 2, t4 = lane & 3;
#pragma unroll 1
  for (int r = 0; r < 2; r++) {
    const int row0 = (bid * 8 + r * 4) * 64 + warp * 16;
    uint32_t qa[8];
    {
      const bf16* q0 = q + (size_t)(row0 + g) * 32 + t4 * 2;
      const bf16* q1 = q0 + 8 * 32;
      qa[0] = *reinterpret_cast<const uint32_t*>(q0);      qa[1] = *reinterpret_cast<const uint32_t*>(q1);
      qa[2] = *reinterpret_cast<const uint32_t*>(q0 + 8);  qa[3] = *reinterpret_cast<const uint32_t*>(q1 + 8);
      qa[4] = *reinterpret_cast<const uint32_t*>(q0 + 16); qa[5] = *reinterpret_cast<const uint32_t*>(q1 + 16);
      qa[6] = *reinterpret_cast<const uint32_t*>(q0 + 24); qa[7] = *reinterpret_cast<const uint32_t*>(q1 + 24);
    }
    if (r == 1 && warp == 2 && lane < 18) {
      if (lane < 4) l2_prefetch(reinterpret_cast<const uint8_t*>(wo) + (size_t)bid * 16384 + lane * 4096, 4096);
      else l2_prefetch(reinterpret_cast<const uint8_t*>(w1) + (size_t)bid * 57344 + (lane - 4) * 4096, 4096);
    }
    __syncwarp();
    float oacc[20];
#pragma unroll
    for (int i = 0; i < 20; i++) oacc[i] = 0.f;
    float nm0 = 0.f, nm1 = 0.f, zb0 = 0.f, zb1 = 0.f;
#pragma unroll 1
    for (int outer = r * 4; outer < r * 4 + 4; outer++) {
      attn_tile<0>(sbase, &tmK, &tmV, outer, warp, lane0, qa, oacc, nm0, nm1, zb0, zb1);
      attn_tile<1>(sbase, &tmK, &tmV, outer, warp, lane0, qa, oacc, nm0, nm1, zb0, zb1);
      attn_tile<2>(sbase, &tmK, &tmV, outer, warp, lane0, qa, oacc, nm0, nm1, zb0, zb1);
      attn_tile<3>(sbase, &tmK, &tmV, outer, warp, lane0, qa, oacc, nm0, nm1, zb0, zb1);
    }
    const float l0 = __shfl_sync(0xffffffffu, oacc[16], lane & ~3);
    const float l1 = __shfl_sync(0xffffffffu, oacc[18], lane & ~3);
    float a0 = 0.f, a1 = 0.f;
#pragma unroll
    for (int i = 0; i < 4; i++) {
      a0 = fmaxf(a0, fmaxf(fabsf(oacc[4 * i]), fabsf(oacc[4 * i + 1])));
      a1 = fmaxf(a1, fmaxf(fabsf(oacc[4 * i + 2]), fabsf(oacc[4 * i + 3])));
      a0 += oacc[4 * i] * 0.f + oacc[4 * i + 1] * 0.f;
      a1 += oacc[4 * i + 2] * 0.f + oacc[4 * i + 3] * 0.f;
    }
    const bool ok0 = (l0 > 0.f) && (l0 < 1.0e38f) && (a0 < 1.0e38f);
    const bool ok1 = (l1 > 0.f) && (l1 < 1.0e38f) && (a1 < 1.0e38f);
    const float i0 = 1.0f / l0, i1 = 1.0f / l1;
    bf16* o0 = o + (size_t)(row0 + g) * 32 + t4 * 2;
    bf16* o1 = o0 + 8 * 32;
#pragma unroll
    for (int i = 0; i < 4; i++) {
      *reinterpret_cast<uint32_t*>(o0 + i * 8) = pack_bf16(oacc[4 * i] * i0, oacc[4 * i + 1] * i0);
      *reinterpret_cast<uint32_t*>(o1 + i * 8) = pack_bf16(oacc[4 * i + 2] * i1, oacc[4 * i + 3] * i1);
    }
    const uint32_t bad0 = __ballot_sync(0xffffffffu, !ok0), bad1 = __ballot_sync(0xffffffffu, !ok1);
    if (bad0 | bad1) {
      __syncwarp();
      for (int rr = 0; rr < 8; rr++) {
        if ((bad0 >> (rr * 4)) & 0xF) attn_slow_row(q, o, row0 + rr, lane);
        if ((bad1 >> (rr * 4)) & 0xF) attn_slow_row(q, o, row0 + 8 + rr, lane);
      }
    }
  }
  TL(2, 3);
}

typedef CUresult (*PFN_encodeTiled)(CUtensorMap*, CUtensorMapDataType, cuuint32_t, void*, const cuuint64_t*,
                                    const cuuint64_t*, const cuuint32_t*, const cuuint32_t*, CUtensorMapInterleave,
                                    CUtensorMapSwizzle, CUtensorMapL2promotion, CUtensorMapFloatOOBfill);
static PFN_encodeTiled g_encode = nullptr;

static CUtensorMap make_map_2d(const void* ptr, uint64_t inner, uint64_t outer, uint64_t pitch_elems, uint32_t box_inner,
                               uint32_t box_outer, CUtensorMapSwizzle sw) {
  CUtensorMap m;
  cuuint64_t dims[2] = {inner, outer};
  cuuint64_t strides[1] = {pitch_elems * 2};
  cuuint32_t box[2] = {box_inner, box_outer};
  cuuint32_t es[2] = {1, 1};
  g_encode(&m, CU_TENSOR_MAP_DATA_TYPE_BFLOAT16, 2, const_cast<void*>(ptr), dims, strides, box, es,
           CU_TENSOR_MAP_INTERLEAVE_NONE, sw, CU_TENSOR_MAP_L2_PROMOTION_L2_256B, CU_TENSOR_MAP_FLOAT_OOB_FILL_NONE);
  return m;
}
static CUtensorMap make_map_w(const void* ptr, uint64_t K, uint64_t N, uint32_t chunk, uint32_t nchunks_box,
                              uint32_t krows_box, CUtensorMapSwizzle sw) {
  CUtensorMap m;
  cuuint64_t dims[3] = {chunk, K, N / chunk};
  cuuint64_t strides[2] = {N * 2, (cuuint64_t)chunk * 2};
  cuuint32_t box[3] = {chunk, krows_box, nchunks_box};
  cuuint32_t es[3] = {1, 1, 1};
  g_encode(&m, CU_TENSOR_MAP_DATA_TYPE_BFLOAT16, 3, const_cast<void*>(ptr), dims, strides, box, es,
           CU_TENSOR_MAP_INTERLEAVE_NONE, sw, CU_TENSOR_MAP_L2_PROMOTION_L2_256B, CU_TENSOR_MAP_FLOAT_OOB_FILL_NONE);
  return m;
}

#define USE_PDL 1

template <typename... KArgs, typename... Args>
static void launch(void (*kern)(KArgs...), int grid, int block, int smem, bool pdl, int cluster, Args... args) {
  cudaLaunchConfig_t cfg = {};
  cfg.gridDim = dim3(grid);
  cfg.blockDim = dim3(block);
  cfg.dynamicSmemBytes = smem;
  cfg.stream = cudaStreamPerThread;
  cudaLaunchAttribute attr[2];
  int na = 0;
  if (pdl && USE_PDL) {
    attr[na].id = cudaLaunchAttributeProgrammaticStreamSerialization;
    attr[na].val.programmaticStreamSerializationAllowed = 1;
    na++;
  }
  if (cluster > 1) {
    attr[na].id = cudaLaunchAttributeClusterDimension;
    attr[na].val.clusterDim.x = cluster; attr[na].val.clusterDim.y = 1; attr[na].val.clusterDim.z = 1;
    na++;
  }
  cfg.attrs = attr;
  cfg.numAttrs = na;
  cudaLaunchKernelEx(&cfg, kern, KArgs(args)...);
}

extern "C" void kernel_launch(void* const* d_in, const int* in_sizes, int n_in, void* d_out, int out_size) {
  const bf16* x = (const bf16*)d_in[0];
  const bf16* wq = (const bf16*)d_in[1];
  const bf16* wk = (const bf16*)d_in[2];
  const bf16* wv = (const bf16*)d_in[3];
  const bf16* wo = (const bf16*)d_in[4];
  const bf16* w1 = (const bf16*)d_in[6];
  const bf16* w2 = (const bf16*)d_in[7];
  const bf16* c = (const bf16*)d_in[8];
  const bf16* wmod = (const bf16*)d_in[9];
  bf16* out = (bf16*)d_out;

#define FF2_NST 7
#define QKV_NST 5
#define OUT_NST 7
#define QKV_CN 1
#define OUT_CM 1
#define OUT_CN 1
#define FF1_CM 2
#define FF1_CN 1
#define FF2_CM 1
#define FF2_CN 2
  auto kQKV = gemm_kernel<136, 0, 1024, QKV_NST, EPI_QKV, 1, 1, QKV_CN>;
  auto kOUT = gemm_kernel<128, 1, 1024, OUT_NST, EPI_RES, 1, OUT_CM, OUT_CN>;
  auto kFF1 = gemm_kernel<224, 2, 1024, 4, EPI_RELU, 2, FF1_CM, FF1_CN>;
  auto kFF2 = gemm_kernel<128, 1, 3584, FF2_NST, EPI_RES, 1, FF2_CM, FF2_CN>;
  constexpr int smQKV = GemmCfg<136, 0, 1024, QKV_NST, EPI_QKV, 1>::SMEM;
  constexpr int smOUT = GemmCfg<128, 1, 1024, OUT_NST, EPI_RES, 1>::SMEM;
  constexpr int smFF1 = GemmCfg<224, 2, 1024, 4, EPI_RELU, 2>::SMEM;
  constexpr int smFF2 = GemmCfg<128, 1, 3584, FF2_NST, EPI_RES, 1>::SMEM;

  static bool inited = false;
  static void *p_h, *p_wqkvT, *p_q, *p_k, *p_vT, *p_o, *p_x1, *p_hff, *p_mod;
  if (!inited) {
    cudaDriverEntryPointQueryResult qr;
    void* fn = nullptr;
    cudaGetDriverEntryPoint("cuTensorMapEncodeTiled", &fn, cudaEnableDefault, &qr);
    g_encode = (PFN_encodeTiled)fn;
    cudaGetSymbolAddress(&p_h, g_h); cudaGetSymbolAddress(&p_wqkvT, g_wqkvT); cudaGetSymbolAddress(&p_q, g_q);
    cudaGetSymbolAddress(&p_k, g_k); cudaGetSymbolAddress(&p_vT, g_vT); cudaGetSymbolAddress(&p_o, g_o);
    cudaGetSymbolAddress(&p_x1, g_x1); cudaGetSymbolAddress(&p_hff, g_hff); cudaGetSymbolAddress(&p_mod, g_mod);
    cudaFuncSetAttribute(kQKV, cudaFuncAttributeMaxDynamicSharedMemorySize, smQKV);
    cudaFuncSetAttribute(kOUT, cudaFuncAttributeMaxDynamicSharedMemorySize, smOUT);
    cudaFuncSetAttribute(kFF1, cudaFuncAttributeMaxDynamicSharedMemorySize, smFF1);
    cudaFuncSetAttribute(kFF2, cudaFuncAttributeMaxDynamicSharedMemorySize, smFF2);
    cudaFuncSetAttribute(attn_kernel, cudaFuncAttributeMaxDynamicSharedMemorySize, ATT_SMEM);
    inited = true;
  }
  const float* mod = (const float*)p_mod;
  const auto SW128 = CU_TENSOR_MAP_SWIZZLE_128B;
  const auto SW64 = CU_TENSOR_MAP_SWIZZLE_64B;

  CUtensorMap mA_h = make_map_2d(p_h, D_, S_, D_, 64, 128 / QKV_CN, SW128);
  CUtensorMap mB_qkv = make_map_2d(p_wqkvT, D_, NQKV, D_, 64, 136, SW128);
  CUtensorMap mC_q = make_map_2d(p_q, D_, S_, D_, 64, 64, SW128);
  CUtensorMap mK = make_map_2d(p_k, 32, S_, 32, 32, ATT_KBOX, SW64);
  CUtensorMap mV = make_map_2d(p_vT, S_, 32, S_, 64, 32, SW128);
  CUtensorMap mA_o = make_map_2d(p_o, D_, S_, D_, 64, 128 / OUT_CN, SW128);
  CUtensorMap mB_wo = make_map_w(wo, D_, D_, 64, OUT_CM == 1 ? 2 : 1, OUT_CM == 4 ? 32 : 64, SW128);
  CUtensorMap mC_x1 = make_map_2d(p_x1, D_, S_, D_, 64, 64, SW128);
  CUtensorMap mC_h = make_map_2d(p_h, D_, S_, D_, 64, 64, SW128);
  CUtensorMap mR_x = make_map_2d(x, D_, S_, D_, 64, 64, SW128);
  CUtensorMap mA_h2 = make_map_2d(p_h, D_, S_, D_, 64, 128 / FF1_CN, SW128);
  CUtensorMap mB_w1 = make_map_w(w1, D_, DFF, 32, 7, 64 / FF1_CM, SW64);
  CUtensorMap mC_hff = make_map_2d(p_hff, DFF, S_, DFF, 32, 64, SW64);
  CUtensorMap mA_hff = make_map_2d(p_hff, DFF, S_, DFF, 64, 128 / FF2_CN, SW128);
  CUtensorMap mB_w2 = make_map_w(w2, DFF, D_, 64, FF2_CM == 1 ? 2 : 1, FF2_CM == 4 ? 32 : 64, SW128);
  CUtensorMap mC_out = make_map_2d(out, D_, S_, D_, 64, 64, SW128);
  const void* nul = nullptr;

  launch(pre_kernel, 136, 512, 0, false, 1, x, c, wmod, wq, wk, wv);
  launch(kQKV, 128, 288, smQKV, true, QKV_CN, mA_h, mB_qkv, mC_q, mC_q, mC_q, mod, nul);
  launch(attn_kernel, ATT_GRID, ATT_THREADS, ATT_SMEM, true, 1, mK, mV, (const bf16*)p_q, (bf16*)p_o, c, wmod, wo, w1);
  launch(kOUT, 128, 288, smOUT, true, OUT_CM * OUT_CN, mA_o, mB_wo, mC_x1, mR_x, mC_h, mod + 2 * D_, nul);
  launch(kFF1, 128, 288, smFF1, true, FF1_CM * FF1_CN, mA_h2, mB_w1, mC_hff, mC_hff, mC_hff, mod, (const void*)w2);
  launch(kFF2, 128, 288, smFF2, true, FF2_CM * FF2_CN, mA_hff, mB_w2, mC_out, mC_x1, mC_x1, mod + 5 * D_, nul);
}
```
